```python
import torch

def _softmax(x, axis=-1):
    return torch.softmax(x, dim=axis)
def _gelu(x):
    return torch.nn.functional.gelu(x, approximate="tanh")
def _silu(x):
    return torch.nn.functional.silu(x)
def _sigmoid(x):
    return torch.sigmoid(x)
def _layernorm(x, axis=-1, eps=1e-5):
    m = x.mean(dim=axis, keepdim=True)
    v = x.var(dim=axis, keepdim=True, unbiased=False)
    return (x - m) / torch.sqrt(v + eps)
def _scatter_add(tgt, idx, src, axis=0):
    return tgt.clone().index_add_(axis, idx, src)
def _segment_sum(src, seg, n):
    out = torch.zeros((n,) + src.shape[1:], dtype=src.dtype)
    return out.index_add_(0, seg, src)
def _pad(x, pw):
    flat = tuple(v for pair in reversed(pw) for v in pair)
    return torch.nn.functional.pad(x, flat)

kernel_name = 'gated_mix__gqa_block_cached__gqa_block_cached__decode'

def setup_inputs():

    _w = (lambda a: (lambda t: t.to(torch.bfloat16) if t.is_floating_point() else t)(torch.as_tensor(a)))
    def _A_setup():
        B, Sq, D = 2, 1, 512
        Hq, Hkv, Sk, Dh = 32, 8, 32768, 128
        assert Hq % Hkv == 0, (Hq, Hkv)
        return {
            "x": _w((lambda *s: torch.randn(*s, dtype=torch.bfloat16) * 0.05)(B, Sq, D)),
            "k_cache": _w((lambda *s: torch.randn(*s, dtype=torch.bfloat16) * 6.4)(B, Hkv, Sk, Dh)),
            "v_cache": _w((lambda *s: torch.randn(*s, dtype=torch.bfloat16) * 0.05)(B, Hkv, Sk, Dh)),
            "wq": _w((lambda *s: torch.randn(*s, dtype=torch.bfloat16) * 6.4)(D, Hq * Dh) * (D ** -0.5)),
            "wo": _w((lambda *s: torch.randn(*s, dtype=torch.bfloat16) * 0.05)(Hq * Dh, D) * ((Hq * Dh) ** -0.5)),
        }
    _A_in = _A_setup()

    def _B_setup():
        B, Sq, D = 2, 1, 512
        Hq, Hkv, Sk, Dh = 32, 8, 32768, 128
        assert Hq % Hkv == 0, (Hq, Hkv)
        return {
            "x": _w((lambda *s: torch.randn(*s, dtype=torch.bfloat16) * 0.05)(B, Sq, D)),
            "k_cache": _w((lambda *s: torch.randn(*s, dtype=torch.bfloat16) * 6.4)(B, Hkv, Sk, Dh)),
            "v_cache": _w((lambda *s: torch.randn(*s, dtype=torch.bfloat16) * 0.05)(B, Hkv, Sk, Dh)),
            "wq": _w((lambda *s: torch.randn(*s, dtype=torch.bfloat16) * 6.4)(D, Hq * Dh) * (D ** -0.5)),
            "wo": _w((lambda *s: torch.randn(*s, dtype=torch.bfloat16) * 0.05)(Hq * Dh, D) * ((Hq * Dh) ** -0.5)),
        }
    _B_in = _B_setup()

    return {
        "A_x": _A_in["x"],
        "A_k_cache": _A_in["k_cache"],
        "A_v_cache": _A_in["v_cache"],
        "A_wq": _A_in["wq"],
        "A_wo": _A_in["wo"],
        "B_x": _B_in["x"],
        "B_k_cache": _B_in["k_cache"],
        "B_v_cache": _B_in["v_cache"],
        "B_wq": _B_in["wq"],
        "B_wo": _B_in["wo"],
        "gate_w": _w((lambda *s: torch.randn(*s, dtype=torch.bfloat16) * 0.1)(512) * 16.0),
    }

def reference(A_x, A_k_cache, A_v_cache, A_wq, A_wo, B_x, B_k_cache, B_v_cache, B_wq, B_wo, gate_w):
    def _A_ref(x, k_cache, v_cache, wq, wo):
        B, Sq, D = x.shape
        Hq, Dh = 32, 128
        Hkv = k_cache.shape[1]
        rep = Hq // Hkv
        q = (lambda x, *d: x.permute(*d))((x @ wq).reshape(B, Sq, Hq, Dh), 0, 2, 1, 3)
        k = (lambda x, n, axis: torch.repeat_interleave(x, n, dim=axis))(k_cache, rep, axis=1)
        v = (lambda x, n, axis: torch.repeat_interleave(x, n, dim=axis))(v_cache, rep, axis=1)
        scores = torch.einsum("bhqd,bhkd->bhqk", q, k) * (Dh ** -0.5)
        p = _softmax(scores, axis=-1)
        o = torch.einsum("bhqk,bhkd->bhqd", p, v)
        return (lambda x, *d: x.permute(*d))(o, 0, 2, 1, 3).reshape(B, Sq, Hq * Dh) @ wo

    def _B_ref(x, k_cache, v_cache, wq, wo):
        B, Sq, D = x.shape
        Hq, Dh = 32, 128
        Hkv = k_cache.shape[1]
        rep = Hq // Hkv
        q = (lambda x, *d: x.permute(*d))((x @ wq).reshape(B, Sq, Hq, Dh), 0, 2, 1, 3)
        k = (lambda x, n, axis: torch.repeat_interleave(x, n, dim=axis))(k_cache, rep, axis=1)
        v = (lambda x, n, axis: torch.repeat_interleave(x, n, dim=axis))(v_cache, rep, axis=1)
        scores = torch.einsum("bhqd,bhkd->bhqk", q, k) * (Dh ** -0.5)
        p = _softmax(scores, axis=-1)
        o = torch.einsum("bhqk,bhkd->bhqd", p, v)
        return (lambda x, *d: x.permute(*d))(o, 0, 2, 1, 3).reshape(B, Sq, Hq * Dh) @ wo

    x = A_x
    g = _sigmoid((x * gate_w).sum(-1, keepdims=True))
    a = _A_ref(x, A_k_cache, A_v_cache, A_wq, A_wo)
    b = _B_ref(x, B_k_cache, B_v_cache, B_wq, B_wo)
    return g * a + (1 - g) * b
```

```cpp
#include <cuda_runtime.h>
#include <cuda_bf16.h>
#include <cuda.h>
#include <stdint.h>

namespace {

constexpr int NCTA        = 128;
#define S_SPLIT 8
constexpr int SPL         = S_SPLIT;
constexpr int NSEG        = SPL / 4;
constexpr int SK          = 32768;
constexpr int TILE_KEYS   = 128;
constexpr int TILES_PER_STREAM = SK / TILE_KEYS;
constexpr int TPS         = TILES_PER_STREAM / SPL;
constexpr int STAGES      = 6;
constexpr int STAGE_BYTES = 32768;
constexpr int NCW         = 8;
constexpr int NTHREADS    = NCW * 32 + 32;

constexpr int SM_RING  = 0;
constexpr int SM_O     = STAGES * STAGE_BYTES;
constexpr int SM_Q     = SM_O + NCW * 512 * 4;
constexpr int SM_M     = SM_Q + NSEG * 256 * 4;
constexpr int SM_L     = SM_M + NCW * 4 * 4;
constexpr int SM_G     = SM_L + NCW * 4 * 4;
constexpr int SM_BAR   = SM_G + 16;
constexpr int SM_TOTAL = SM_BAR + 2 * STAGES * 8;
constexpr int SM_ALLOC = SM_TOTAL + 1024;

struct Params {
    CUtensorMap kv[4];
    CUtensorMap wq[2];
    CUtensorMap wo[2];
    const __nv_bfloat16* x;
    const __nv_bfloat16* gate_w;
    __nv_bfloat16* out;
};

typedef unsigned long long u64;

__device__ unsigned int g_epoch;
__device__ u64 g_q[2 * 2 * 2048];
__device__ u64 g_partO[32 * SPL * 8 * 64];
__device__ u64 g_partML[32 * SPL * 8 * 2];
__device__ u64 g_outp[NCTA * NCTA * 8];

__device__ __forceinline__ uint32_t smem_u32(const void* p) { return (uint32_t)__cvta_generic_to_shared(p); }
__device__ __forceinline__ void mbar_init(uint32_t bar, uint32_t cnt) {
    asm volatile("mbarrier.init.shared::cta.b64 [%0], %1;" :: "r"(bar), "r"(cnt) : "memory");
}
__device__ __forceinline__ void mbar_expect_tx(uint32_t bar, uint32_t bytes) {
    asm volatile("mbarrier.arrive.expect_tx.shared::cta.b64 _, [%0], %1;" :: "r"(bar), "r"(bytes) : "memory");
}
__device__ __forceinline__ void mbar_arrive(uint32_t bar) {
    asm volatile("mbarrier.arrive.shared::cta.b64 _, [%0];" :: "r"(bar) : "memory");
}
__device__ __forceinline__ bool mbar_try(uint32_t bar, uint32_t parity) {
    uint32_t ok;
    asm volatile("{\n.reg .pred p;\nmbarrier.try_wait.parity.shared::cta.b64 p, [%1], %2;\nselp.u32 %0, 1, 0, p;\n}"
                 : "=r"(ok) : "r"(bar), "r"(parity) : "memory");
    return ok != 0;
}
__device__ __forceinline__ void mbar_wait(uint32_t bar, uint32_t parity) {
    uint32_t spins = 0;
    while (!mbar_try(bar, parity)) {
        if (++spins > (1u << 24)) __trap();
    }
}
__device__ __forceinline__ void tma2d(uint32_t dst, const CUtensorMap* m, int c0, int c1, uint32_t bar, u64 pol) {
    asm volatile("cp.async.bulk.tensor.2d.shared::cluster.global.mbarrier::complete_tx::bytes.L2::cache_hint "
                 "[%0], [%1, {%3, %4}], [%2], %5;"
                 :: "r"(dst), "l"(m), "r"(bar), "r"(c0), "r"(c1), "l"(pol) : "memory");
}
__device__ __forceinline__ void ldsm4(uint32_t& r0, uint32_t& r1, uint32_t& r2, uint32_t& r3, uint32_t addr) {
    asm volatile("ldmatrix.sync.aligned.m8n8.x4.shared.b16 {%0,%1,%2,%3}, [%4];"
                 : "=r"(r0), "=r"(r1), "=r"(r2), "=r"(r3) : "r"(addr) : "memory");
}
__device__ __forceinline__ void ldsm4t(uint32_t& r0, uint32_t& r1, uint32_t& r2, uint32_t& r3, uint32_t addr) {
    asm volatile("ldmatrix.sync.aligned.m8n8.x4.trans.shared.b16 {%0,%1,%2,%3}, [%4];"
                 : "=r"(r0), "=r"(r1), "=r"(r2), "=r"(r3) : "r"(addr) : "memory");
}
__device__ __forceinline__ void mma16816(float* d, uint32_t a0, uint32_t a1, uint32_t a2, uint32_t a3,
                                         uint32_t b0, uint32_t b1) {
    asm volatile("mma.sync.aligned.m16n8k16.row.col.f32.bf16.bf16.f32 {%0,%1,%2,%3}, {%4,%5,%6,%7}, {%8,%9}, {%0,%1,%2,%3};"
                 : "+f"(d[0]), "+f"(d[1]), "+f"(d[2]), "+f"(d[3])
                 : "r"(a0), "r"(a1), "r"(a2), "r"(a3), "r"(b0), "r"(b1));
}
__device__ __forceinline__ uint32_t pack_bf16(float lo, float hi) {
    uint32_t r;
    asm("cvt.rn.bf16x2.f32 %0, %1, %2;" : "=r"(r) : "f"(hi), "f"(lo));
    return r;
}
__device__ __forceinline__ float ex2(float x) {
    float r;
    asm("ex2.approx.ftz.f32 %0, %1;" : "=f"(r) : "f"(x));
    return r;
}
__device__ __forceinline__ void consumer_sync() { asm volatile("bar.sync 1, 256;" ::: "memory"); }

__device__ __forceinline__ u64 mk_slot(uint32_t payload, uint32_t tag) { return ((u64)tag << 32) | payload; }
__device__ __forceinline__ void st_slot(u64* p, u64 v) {
    asm volatile("st.relaxed.gpu.global.u64 [%0], %1;" :: "l"(p), "l"(v) : "memory");
}
__device__ __forceinline__ void st_slot2(u64* p, u64 a, u64 b) {
    asm volatile("st.relaxed.gpu.global.v2.u64 [%0], {%1,%2};" :: "l"(p), "l"(a), "l"(b) : "memory");
}
__device__ __forceinline__ u64 ld_slot(const u64* p) {
    u64 v;
    asm volatile("ld.relaxed.gpu.global.u64 %0, [%1];" : "=l"(v) : "l"(p) : "memory");
    return v;
}
__device__ __forceinline__ void ld_slot2(const u64* p, u64& a, u64& b) {
    asm volatile("ld.relaxed.gpu.global.v2.u64 {%0,%1}, [%2];" : "=l"(a), "=l"(b) : "l"(p) : "memory");
}
__device__ __forceinline__ uint32_t slot_tag(u64 v) { return (uint32_t)(v >> 32); }
__device__ __forceinline__ uint32_t slot_val(u64 v) { return (uint32_t)v; }
__device__ __forceinline__ void poll_slot(const u64* p, u64& v, uint32_t tag) {
    uint32_t spins = 0;
    while (slot_tag(v) != tag) {
        if (++spins > (1u << 22)) __trap();
        v = ld_slot(p);
    }
}
__device__ __forceinline__ void poll_slot2(const u64* p, u64& a, u64& b, uint32_t tag) {
    uint32_t spins = 0;
    while (slot_tag(a) != tag || slot_tag(b) != tag) {
        if (++spins > (1u << 22)) __trap();
        ld_slot2(p, a, b);
    }
}

__global__ void __launch_bounds__(NTHREADS, 1)
fused_decode_kernel(const __grid_constant__ Params P) {
    extern __shared__ unsigned char smem_raw[];
    const uint32_t sbase = (smem_u32(smem_raw) + 1023u) & ~1023u;
    unsigned char* sgen = smem_raw + (sbase - smem_u32(smem_raw));
    const uint32_t bar_full = sbase + SM_BAR;
    const uint32_t bar_empty = bar_full + STAGES * 8;

    const int tid = threadIdx.x;
    const int warp = tid >> 5;
    const int lane = tid & 31;
    const int cta = blockIdx.x;
    const int grp = cta / SPL;
    const int jsp = cta % SPL;
    const int cbr = cta >> 6;
    const int csl = cta & 63;

    if (warp == NCW) {
        if (lane == 0) {
#pragma unroll
            for (int s = 0; s < STAGES; s++) {
                mbar_init(bar_full + s * 8, 1);
                mbar_init(bar_empty + s * 8, NCW);
            }
            asm volatile("fence.mbarrier_init.release.cluster;" ::: "memory");
            asm volatile("fence.proxy.async.shared::cta;" ::: "memory");
        }
        __syncwarp();
        u64 pol;
        asm volatile("createpolicy.fractional.L2::evict_first.b64 %0, 1.0;" : "=l"(pol));
        if (lane == 0) {
            mbar_expect_tx(bar_full + 0, STAGE_BYTES);
            tma2d(sbase + SM_RING, &P.wq[cbr], csl * 64, 0, bar_full + 0, pol);
            mbar_expect_tx(bar_full + 8, STAGE_BYTES);
            tma2d(sbase + SM_RING + STAGE_BYTES, &P.wq[cbr], csl * 64, 256, bar_full + 8, pol);
        }
        __syncthreads();
        if (lane == 0) {
            int stage = 2;
            uint32_t ph = 1;
            for (int sg = 0; sg < NSEG; sg++) {
                const int sidx = grp * NSEG + sg;
                const int br = sidx >> 4;
                const CUtensorMap* mk = &P.kv[br * 2];
                const CUtensorMap* mv = &P.kv[br * 2 + 1];
                int row = (sidx & 15) * (SK * 2) + jsp * (TILE_KEYS * 2);
                for (int tt = 0; tt < TPS; tt++) {
                    mbar_wait(bar_empty + stage * 8, ph);
                    mbar_expect_tx(bar_full + stage * 8, STAGE_BYTES);
                    tma2d(sbase + SM_RING + stage * STAGE_BYTES, mk, 0, row, bar_full + stage * 8, pol);
                    if (++stage == STAGES) { stage = 0; ph ^= 1; }
                    mbar_wait(bar_empty + stage * 8, ph);
                    mbar_expect_tx(bar_full + stage * 8, STAGE_BYTES);
                    tma2d(sbase + SM_RING + stage * STAGE_BYTES, mv, 0, row, bar_full + stage * 8, pol);
                    if (++stage == STAGES) { stage = 0; ph ^= 1; }
                    row += SPL * TILE_KEYS * 2;
                }
            }
            for (int hs = 0; hs < 2; hs++) {
                mbar_wait(bar_empty + stage * 8, ph);
                mbar_expect_tx(bar_full + stage * 8, STAGE_BYTES);
#pragma unroll
                for (int bx = 0; bx < 4; bx++)
                    tma2d(sbase + SM_RING + stage * STAGE_BYTES + bx * 8192, &P.wo[cbr], (hs * 4 + bx) * 64, csl * 64,
                          bar_full + stage * 8, pol);
                if (++stage == STAGES) { stage = 0; ph ^= 1; }
            }
        }
        return;
    }

    const int g = lane >> 2;
    const int t = lane & 3;
    float* sO = reinterpret_cast<float*>(sgen + SM_O);
    uint32_t* sQ = reinterpret_cast<uint32_t*>(sgen + SM_Q);
    float* sM = reinterpret_cast<float*>(sgen + SM_M);
    float* sL = reinterpret_cast<float*>(sgen + SM_L);
    float* sG = reinterpret_cast<float*>(sgen + SM_G);

    const uint32_t tag = *(volatile unsigned int*)&g_epoch + 1u;

    uint32_t xb[4][2];
    {
        const uint32_t* x32 = reinterpret_cast<const uint32_t*>(P.x);
#pragma unroll
        for (int ks = 0; ks < 4; ks++) {
            const int d = warp * 64 + ks * 16 + 2 * t;
            xb[ks][0] = (g < 2) ? __ldg(x32 + ((g * 512 + d) >> 1)) : 0u;
            xb[ks][1] = (g < 2) ? __ldg(x32 + ((g * 512 + d + 8) >> 1)) : 0u;
        }
    }
    if (warp < 2) {
        const uint4* x16 = reinterpret_cast<const uint4*>(P.x + warp * 512);
        const uint4* g16 = reinterpret_cast<const uint4*>(P.gate_w);
        float acc = 0.f;
#pragma unroll
        for (int i = 0; i < 2; i++) {
            uint4 a = __ldg(x16 + lane + i * 32), b = __ldg(g16 + lane + i * 32);
            const uint32_t av[4] = {a.x, a.y, a.z, a.w}, bv[4] = {b.x, b.y, b.z, b.w};
#pragma unroll
            for (int k = 0; k < 4; k++) {
                acc += __uint_as_float(av[k] << 16) * __uint_as_float(bv[k] << 16);
                acc += __uint_as_float(av[k] & 0xffff0000u) * __uint_as_float(bv[k] & 0xffff0000u);
            }
        }
#pragma unroll
        for (int o = 16; o > 0; o >>= 1) acc += __shfl_xor_sync(0xffffffffu, acc, o);
        if (lane == 0) sG[warp] = 1.f / (1.f + __expf(-acc));
    }
    __syncthreads();

    const int lrow = (lane & 7) + ((lane >> 4) << 3);
    const int lchk = (lane >> 3) & 1;

    {
        const int st = warp >> 2;
        mbar_wait(bar_full + st * 8, 0);
        float acc[4][4];
#pragma unroll
        for (int i = 0; i < 4; i++) { acc[i][0] = acc[i][1] = acc[i][2] = acc[i][3] = 0.f; }
        const uint32_t base = sbase + SM_RING + st * STAGE_BYTES + ((warp & 3) * 64 + lrow) * 128;
#pragma unroll
        for (int ks = 0; ks < 4; ks++) {
#pragma unroll
            for (int i = 0; i < 4; i++) {
                uint32_t a0, a1, a2, a3;
                ldsm4t(a0, a1, a2, a3, base + ks * 2048 + (((2 * i + lchk) ^ (lane & 7)) << 4));
                mma16816(acc[i], a0, a1, a2, a3, xb[ks][0], xb[ks][1]);
            }
        }
        __syncwarp();
        if (lane == 0) { mbar_arrive(bar_empty + 0); mbar_arrive(bar_empty + 8); }
        if (t == 0) {
#pragma unroll
            for (int i = 0; i < 4; i++) {
                sO[warp * 128 + 0 * 64 + 16 * i + g] = acc[i][0];
                sO[warp * 128 + 1 * 64 + 16 * i + g] = acc[i][1];
                sO[warp * 128 + 0 * 64 + 16 * i + g + 8] = acc[i][2];
                sO[warp * 128 + 1 * 64 + 16 * i + g + 8] = acc[i][3];
            }
        }
        consumer_sync();
        if (tid < 64) {
            const int b = tid >> 5, cp = tid & 31;
            float s0 = 0.f, s1 = 0.f;
#pragma unroll
            for (int w = 0; w < NCW; w++) {
                float2 v = *reinterpret_cast<const float2*>(&sO[w * 128 + b * 64 + 2 * cp]);
                s0 += v.x; s1 += v.y;
            }
            st_slot(&g_q[(cbr * 2 + b) * 2048 + csl * 32 + cp], mk_slot(pack_bf16(s0, s1), tag));
        }
        u64 qs[NSEG];
#pragma unroll
        for (int sg = 0; sg < NSEG; sg++) {
            const int sidx = grp * NSEG + sg;
            qs[sg] = ld_slot(&g_q[(sidx >> 3) * 2048 + (sidx & 7) * 256 + tid]);
        }
#pragma unroll
        for (int sg = 0; sg < NSEG; sg++) {
            const int sidx = grp * NSEG + sg;
            poll_slot(&g_q[(sidx >> 3) * 2048 + (sidx & 7) * 256 + tid], qs[sg], tag);
            sQ[sg * 256 + tid] = slot_val(qs[sg]);
        }
        consumer_sync();
    }

    const float CS = 0.08838834764831845f * 1.4426950408889634f;
    const bool active = (g >> 2) == (t >> 1);
    uint32_t offK[2], offV[2];
#pragma unroll
    for (int h = 0; h < 2; h++) {
        const int half = h ^ ((lane & 7) >> 2);
        const int swz = 2 * (lane & 3) + half;
        const int rk = 2 * (warp * 16 + (lane & 7)) + half;
        offK[h] = rk * 128 + (((lane >> 3) ^ swz) << 4);
        const int rv = 2 * (warp * 16 + lrow) + half;
        offV[h] = rv * 128 + ((lchk ^ swz) << 4);
    }

    int stage = 2;
    uint32_t ph = 0;
    for (int sg = 0; sg < NSEG; sg++) {
        uint32_t qf[2][4][2];
#pragma unroll
        for (int h = 0; h < 2; h++)
#pragma unroll
            for (int j = 0; j < 4; j++) {
                const int w0 = sg * 256 + (((g & 3) * 128 + (h ^ (g >> 2)) * 64 + 16 * j) >> 1) + t;
                qf[h][j][0] = sQ[w0];
                qf[h][j][1] = sQ[w0 + 4];
            }
        float o[2][4][4];
#pragma unroll
        for (int h = 0; h < 2; h++)
#pragma unroll
            for (int c = 0; c < 4; c++) { o[h][c][0] = o[h][c][1] = o[h][c][2] = o[h][c][3] = 0.f; }
        float m = -INFINITY, l = 0.f;

        for (int tt = 0; tt < TPS; tt++) {
            const uint32_t kb = sbase + SM_RING + stage * STAGE_BYTES;
            mbar_wait(bar_full + stage * 8, ph);
            float sc[2][2][4];
#pragma unroll
            for (int nt = 0; nt < 2; nt++)
#pragma unroll
                for (int h = 0; h < 2; h++) {
                    sc[nt][h][0] = sc[nt][h][1] = sc[nt][h][2] = sc[nt][h][3] = 0.f;
#pragma unroll
                    for (int c2 = 0; c2 < 2; c2++) {
                        uint32_t r0, r1, r2, r3;
                        ldsm4(r0, r1, r2, r3, kb + nt * 2048 + (offK[h] ^ (c2 * 64)));
                        mma16816(sc[nt][h], qf[h][2 * c2][0], 0u, qf[h][2 * c2][1], 0u, r0, r1);
                        mma16816(sc[nt][h], qf[h][2 * c2 + 1][0], 0u, qf[h][2 * c2 + 1][1], 0u, r2, r3);
                    }
                }
            __syncwarp();
            if (lane == 0) mbar_arrive(bar_empty + stage * 8);
            if (++stage == STAGES) { stage = 0; ph ^= 1; }

            const float s0 = sc[0][0][0] + sc[0][1][0];
            const float s1 = sc[0][0][1] + sc[0][1][1];
            const float s2 = sc[1][0][0] + sc[1][1][0];
            const float s3 = sc[1][0][1] + sc[1][1][1];
            float mx = fmaxf(fmaxf(s0, s1), fmaxf(s2, s3));
            mx = fmaxf(mx, __shfl_xor_sync(0xffffffffu, mx, 1));
            mx = fmaxf(mx, __shfl_xor_sync(0xffffffffu, mx, 18));
            if (__any_sync(0xffffffffu, active && (mx > m))) {
                const float mn = fmaxf(m, mx);
                const float alpha = ex2((m - mn) * CS);
                m = mn;
                l *= alpha;
                const float a0 = __shfl_sync(0xffffffffu, alpha, (2 * (t & 1)) * 4);
                const float a1 = __shfl_sync(0xffffffffu, alpha, (2 * (t & 1) + 1) * 4);
#pragma unroll
                for (int h = 0; h < 2; h++)
#pragma unroll
                    for (int c = 0; c < 4; c++) {
                        o[h][c][0] *= a0; o[h][c][1] *= a1; o[h][c][2] *= a0; o[h][c][3] *= a1;
                    }
            }
            const float mc = m * CS;
            const float p0 = ex2(fmaf(s0, CS, -mc));
            const float p1 = ex2(fmaf(s1, CS, -mc));
            const float p2 = ex2(fmaf(s2, CS, -mc));
            const float p3 = ex2(fmaf(s3, CS, -mc));
            l += (p0 + p1) + (p2 + p3);
            const uint32_t b0 = active ? pack_bf16(p0, p1) : 0u;
            const uint32_t b1 = active ? pack_bf16(p2, p3) : 0u;

            const uint32_t vb = sbase + SM_RING + stage * STAGE_BYTES;
            mbar_wait(bar_full + stage * 8, ph);
#pragma unroll
            for (int h = 0; h < 2; h++)
#pragma unroll
                for (int c = 0; c < 4; c++) {
                    uint32_t r0, r1, r2, r3;
                    ldsm4t(r0, r1, r2, r3, vb + (offV[h] ^ (c * 32)));
                    mma16816(o[h][c], r0, r1, r2, r3, b0, b1);
                }
            __syncwarp();
            if (lane == 0) mbar_arrive(bar_empty + stage * 8);
            if (++stage == STAGES) { stage = 0; ph ^= 1; }
        }

        l += __shfl_xor_sync(0xffffffffu, l, 1);
        l += __shfl_xor_sync(0xffffffffu, l, 18);
        if (t == 0 && g < 4) sM[warp * 4 + g] = m;
        consumer_sync();
        {
            const int h0 = 2 * (t & 1);
            float M0 = -INFINITY, M1 = -INFINITY;
#pragma unroll
            for (int w = 0; w < NCW; w++) {
                const float2 v = *reinterpret_cast<const float2*>(&sM[w * 4 + h0]);
                M0 = fmaxf(M0, v.x); M1 = fmaxf(M1, v.y);
            }
            const float2 mine = *reinterpret_cast<const float2*>(&sM[warp * 4 + h0]);
            const float f0 = ex2((mine.x - M0) * CS), f1 = ex2((mine.y - M1) * CS);
            const float fa = __shfl_sync(0xffffffffu, f0, (g >> 1) & 1);
            const float fb = __shfl_sync(0xffffffffu, f1, (g >> 1) & 1);
            if (t == 0 && g < 4) sL[warp * 4 + g] = l * ((g & 1) ? fb : fa);
            float* dst = sO + warp * 512 + h0 * 128 + (t >> 1) * 64 + g;
#pragma unroll
            for (int c = 0; c < 4; c++) {
                const float r0 = o[0][c][0] + __shfl_xor_sync(0xffffffffu, o[1][c][0], 2);
                const float r1 = o[0][c][1] + __shfl_xor_sync(0xffffffffu, o[1][c][1], 2);
                const float r2 = o[0][c][2] + __shfl_xor_sync(0xffffffffu, o[1][c][2], 2);
                const float r3 = o[0][c][3] + __shfl_xor_sync(0xffffffffu, o[1][c][3], 2);
                dst[16 * c] = r0 * f0;
                dst[128 + 16 * c] = r1 * f1;
                dst[16 * c + 8] = r2 * f0;
                dst[128 + 16 * c + 8] = r3 * f1;
            }
            consumer_sync();
            const int sidx = grp * NSEG + sg;
            float a = 0.f, b = 0.f;
#pragma unroll
            for (int w = 0; w < NCW; w++) {
                const float2 v = *reinterpret_cast<const float2*>(&sO[w * 512 + 2 * tid]);
                a += v.x; b += v.y;
            }
            st_slot2(&g_partO[(size_t)(sidx * SPL + jsp) * 512 + 2 * tid],
                     mk_slot(__float_as_uint(a), tag), mk_slot(__float_as_uint(b), tag));
            if (tid < 8) {
                const int hd = tid >> 1;
                float M = -INFINITY, L = 0.f;
#pragma unroll
                for (int w = 0; w < NCW; w++) { M = fmaxf(M, sM[w * 4 + hd]); L += sL[w * 4 + hd]; }
                st_slot2(&g_partML[(size_t)((sidx * SPL + jsp) * 8 + tid) * 2],
                         mk_slot(__float_as_uint(M), tag), mk_slot(__float_as_uint(L), tag));
            }
        }
    }

    {
        const int head = csl >> 1;
        const int hh = (head & 3) * 2 + (csl & 1);
        const int b = warp & 1;
        const int sidx = cbr * 16 + b * 8 + (head >> 2);
        constexpr int NJ = SPL / 4;
        u64 oa[NJ], ob[NJ];
        const u64* pO = &g_partO[(size_t)(sidx * SPL + (warp >> 1)) * 512 + hh * 64 + 2 * lane];
#pragma unroll
        for (int i = 0; i < NJ; i++) ld_slot2(pO + (size_t)i * 4 * 512, oa[i], ob[i]);
        float mj = -INFINITY, lj = 0.f;
        if (lane < SPL) {
            const u64* pML = &g_partML[(size_t)((sidx * SPL + lane) * 8 + hh) * 2];
            u64 a, c;
            ld_slot2(pML, a, c);
            poll_slot2(pML, a, c, tag);
            mj = __uint_as_float(slot_val(a));
            lj = __uint_as_float(slot_val(c));
        }
        __syncwarp();
        float M = mj;
#pragma unroll
        for (int o = 16; o > 0; o >>= 1) M = fmaxf(M, __shfl_xor_sync(0xffffffffu, M, o));
        const float wj = ex2((mj - M) * CS);
        float L = wj * lj;
#pragma unroll
        for (int o = 16; o > 0; o >>= 1) L += __shfl_xor_sync(0xffffffffu, L, o);
        const float gate = sG[b];
        const float cj = wj * ((cbr == 0 ? gate : 1.f - gate) / L);
        float a0 = 0.f, a1 = 0.f;
#pragma unroll
        for (int i = 0; i < NJ; i++) {
            poll_slot2(pO + (size_t)i * 4 * 512, oa[i], ob[i], tag);
            const float c = __shfl_sync(0xffffffffu, cj, (warp >> 1) + 4 * i);
            a0 = fmaf(c, __uint_as_float(slot_val(oa[i])), a0);
            a1 = fmaf(c, __uint_as_float(slot_val(ob[i])), a1);
        }
        consumer_sync();
        *reinterpret_cast<float2*>(&sO[warp * 64 + 2 * lane]) = make_float2(a0, a1);
        consumer_sync();
    }
    {
        uint32_t ob[4][2];
#pragma unroll
        for (int ks = 0; ks < 4; ks++)
#pragma unroll
            for (int u = 0; u < 2; u++) {
                float v0 = 0.f, v1 = 0.f;
                const int b = (g >> 1) & 1;
#pragma unroll
                for (int w = 0; w < 4; w++) {
                    const float2 v = *reinterpret_cast<const float2*>(&sO[(2 * w + b) * 64 + ks * 16 + u * 8 + 2 * t]);
                    v0 += v.x; v1 += v.y;
                }
                const uint32_t hi = pack_bf16(v0, v1);
                const uint32_t lo = pack_bf16(v0 - __uint_as_float(hi << 16), v1 - __uint_as_float(hi & 0xffff0000u));
                ob[ks][u] = (g < 4) ? ((g & 1) ? lo : hi) : 0u;
            }
        int st = stage + (warp >> 2);
        uint32_t sph = ph;
        if (st >= STAGES) { st -= STAGES; sph ^= 1; }
        mbar_wait(bar_full + st * 8, sph);
        float acc[4][4];
#pragma unroll
        for (int i = 0; i < 4; i++) { acc[i][0] = acc[i][1] = acc[i][2] = acc[i][3] = 0.f; }
        const uint32_t base = sbase + SM_RING + st * STAGE_BYTES + (warp & 3) * 8192 + lrow * 128;
#pragma unroll
        for (int ks = 0; ks < 4; ks++)
#pragma unroll
            for (int i = 0; i < 4; i++) {
                uint32_t a0, a1, a2, a3;
                ldsm4t(a0, a1, a2, a3, base + ks * 2048 + (((2 * i + lchk) ^ (lane & 7)) << 4));
                mma16816(acc[i], a0, a1, a2, a3, ob[ks][0], ob[ks][1]);
            }
        if (t < 2) {
#pragma unroll
            for (int i = 0; i < 4; i++) {
                const int f = t * 64 + warp * 8 + 2 * i;
                st_slot(&g_outp[((size_t)f * NCTA + cta) * 8 + g], mk_slot(__float_as_uint(acc[i][0] + acc[i][1]), tag));
                st_slot(&g_outp[((size_t)(f + 1) * NCTA + cta) * 8 + g], mk_slot(__float_as_uint(acc[i][2] + acc[i][3]), tag));
            }
        }
    }
    {
        const u64* p = &g_outp[(size_t)cta * NCTA * 8 + 2 * tid];
        u64 a0, b0, a1, b1;
        ld_slot2(p, a0, b0);
        ld_slot2(p + 512, a1, b1);
        poll_slot2(p, a0, b0, tag);
        poll_slot2(p + 512, a1, b1, tag);
        float x0 = __uint_as_float(slot_val(a0)) + __uint_as_float(slot_val(a1));
        float x1 = __uint_as_float(slot_val(b0)) + __uint_as_float(slot_val(b1));
#pragma unroll
        for (int o = 4; o < 32; o <<= 1) {
            x0 += __shfl_xor_sync(0xffffffffu, x0, o);
            x1 += __shfl_xor_sync(0xffffffffu, x1, o);
        }
        float* sR = sO + 1024;
        if (lane < 4) *reinterpret_cast<float2*>(&sR[warp * 8 + 2 * lane]) = make_float2(x0, x1);
        consumer_sync();
        if (tid < 4) {
            float y0 = 0.f, y1 = 0.f;
#pragma unroll
            for (int w = 0; w < NCW; w++) {
                const float2 v = *reinterpret_cast<const float2*>(&sR[w * 8 + 2 * tid]);
                y0 += v.x; y1 += v.y;
            }
            reinterpret_cast<uint32_t*>(P.out)[cta * 4 + tid] = pack_bf16(y0, y1);
            if (cta == 0 && tid == 0) *(volatile unsigned int*)&g_epoch = tag;
        }
    }
}

typedef CUresult (*EncodeFn)(CUtensorMap*, CUtensorMapDataType, cuuint32_t, void*, const cuuint64_t*,
                             const cuuint64_t*, const cuuint32_t*, const cuuint32_t*, CUtensorMapInterleave,
                             CUtensorMapSwizzle, CUtensorMapL2promotion, CUtensorMapFloatOOBfill);

void encode2d(EncodeFn enc, CUtensorMap* m, const void* ptr, uint64_t cols, uint64_t rows, uint32_t box_cols,
              uint32_t box_rows) {
    cuuint64_t dims[2] = {cols, rows};
    cuuint64_t strides[1] = {cols * 2};
    cuuint32_t box[2] = {box_cols, box_rows};
    cuuint32_t es[2] = {1, 1};
    enc(m, CU_TENSOR_MAP_DATA_TYPE_BFLOAT16, 2, const_cast<void*>(ptr), dims, strides, box, es,
        CU_TENSOR_MAP_INTERLEAVE_NONE, CU_TENSOR_MAP_SWIZZLE_128B, CU_TENSOR_MAP_L2_PROMOTION_L2_256B,
        CU_TENSOR_MAP_FLOAT_OOB_FILL_NONE);
}

}

extern "C" void kernel_launch(void* const* d_in, const int* in_sizes, int n_in, void* d_out, int out_size) {
    (void)in_sizes; (void)n_in; (void)out_size;
    static EncodeFn enc = nullptr;
    if (!enc) {
        cudaDriverEntryPointQueryResult qr;
        void* fn = nullptr;
        cudaGetDriverEntryPoint("cuTensorMapEncodeTiled", &fn, cudaEnableDefault, &qr);
        enc = (EncodeFn)fn;
        cudaFuncSetAttribute(fused_decode_kernel, cudaFuncAttributeMaxDynamicSharedMemorySize, SM_ALLOC);
    }
    Params P;
    const uint64_t kvrows = 2ull * 8 * SK * 2;
    encode2d(enc, &P.kv[0], d_in[1], 64, kvrows, 64, 256);
    encode2d(enc, &P.kv[1], d_in[2], 64, kvrows, 64, 256);
    encode2d(enc, &P.kv[2], d_in[6], 64, kvrows, 64, 256);
    encode2d(enc, &P.kv[3], d_in[7], 64, kvrows, 64, 256);
    encode2d(enc, &P.wq[0], d_in[3], 4096, 512, 64, 256);
    encode2d(enc, &P.wq[1], d_in[8], 4096, 512, 64, 256);
    encode2d(enc, &P.wo[0], d_in[4], 512, 4096, 64, 64);
    encode2d(enc, &P.wo[1], d_in[9], 512, 4096, 64, 64);
    P.x = (const __nv_bfloat16*)d_in[0];
    P.gate_w = (const __nv_bfloat16*)d_in[10];
    P.out = (__nv_bfloat16*)d_out;
    fused_decode_kernel<<<NCTA, NTHREADS, SM_ALLOC, cudaStreamPerThread>>>(P);
}
```

```cpp
#include <cuda_runtime.h>
#include <cuda_bf16.h>
#include <cuda.h>
#include <stdint.h>

namespace {

constexpr int MAX_CTA     = 160;
constexpr int NFIN        = 128;
constexpr int SK          = 32768;
constexpr int TILE_KEYS   = 128;
constexpr int NMAIN       = 224;
constexpr int NLATE       = 32;
constexpr int UMAIN       = 32 * NMAIN;
constexpr int UTOTAL      = 32 * (NMAIN + NLATE);
constexpr int RGEN        = 8;
constexpr int NGEN        = (32 + RGEN - 1) / RGEN + 1;
constexpr int STAGES      = 10;
constexpr int STAGE_BYTES = 16384;
constexpr int DEPTH       = 6;
constexpr int WO_NEED     = 5;
constexpr uint32_t PACE      = 264;
constexpr uint32_t PACE_LATE = 200;
constexpr int NCW         = 8;
constexpr int NTHREADS    = (NCW + 4) * 32;
static_assert(NMAIN + NLATE == SK / TILE_KEYS && NMAIN % 32 == 0 && NLATE == 32, "tile split");

constexpr int P_PITCH  = 272;
constexpr int SM_RING  = 0;
constexpr int Q_PITCH  = 288;
constexpr int SM_Q     = STAGES * STAGE_BYTES;
constexpr int SM_RED   = SM_Q + 32 * Q_PITCH * 4;
constexpr int SM_P     = SM_RED + NCW * 128 * 4;
constexpr int SM_M     = SM_P + 4 * P_PITCH;
constexpr int SM_L     = SM_M + NCW * 4 * 4;
constexpr int SM_C     = SM_L + NCW * 4 * 4;
constexpr int SM_R     = SM_C + 256;
constexpr int SM_G     = SM_R + 256;
constexpr int SM_MAIL  = SM_G + 16;
constexpr int SM_BAR   = SM_MAIL + 32;
constexpr int SM_TOTAL = SM_BAR + 2 * STAGES * 8 + 8;
constexpr int SM_ALLOC = SM_TOTAL + 1024;

struct Params {
    CUtensorMap kv[4];
    CUtensorMap wq[2];
    CUtensorMap wo[2];
    const __nv_bfloat16* x;
    const __nv_bfloat16* gate_w;
    __nv_bfloat16* out;
};

typedef unsigned long long u64;

constexpr int NSLOT = RGEN * NMAIN;
static_assert(32 * NLATE <= (RGEN - 1) * NMAIN, "late tiles reuse the oldest slot groups");
__device__ unsigned int g_epoch;
__device__ unsigned int g_ctr[2];
__device__ __align__(128) u64 g_q[32 * 256];
__device__ __align__(128) uint32_t g_partO[NSLOT * 512];
__device__ __align__(128) uint32_t g_partML[4 * NSLOT * 2];
__device__ __align__(128) uint32_t g_cons[32 * 8];
__device__ __align__(128) uint32_t g_outp[NFIN * NFIN * 8];
__device__ __align__(128) uint32_t g_done[32];

__device__ __forceinline__ uint32_t smem_u32(const void* p) { return (uint32_t)__cvta_generic_to_shared(p); }
__device__ __forceinline__ void mbar_init(uint32_t bar, uint32_t cnt) {
    asm volatile("mbarrier.init.shared::cta.b64 [%0], %1;" :: "r"(bar), "r"(cnt) : "memory");
}
__device__ __forceinline__ void mbar_expect_tx(uint32_t bar, uint32_t bytes) {
    asm volatile("mbarrier.arrive.expect_tx.shared::cta.b64 _, [%0], %1;" :: "r"(bar), "r"(bytes) : "memory");
}
__device__ __forceinline__ void mbar_arrive(uint32_t bar) {
    asm volatile("mbarrier.arrive.shared::cta.b64 _, [%0];" :: "r"(bar) : "memory");
}
__device__ __forceinline__ void mbar_wait(uint32_t bar, uint32_t parity) {
    asm volatile("{\n"
                 ".reg .pred p;\n"
                 ".reg .u32 n;\n"
                 "mov.u32 n, 0;\n"
                 "LAB_WAIT:\n"
                 "mbarrier.try_wait.parity.shared::cta.b64 p, [%0], %1;\n"
                 "@p bra LAB_DONE;\n"
                 "add.u32 n, n, 1;\n"
                 "setp.gt.u32 p, n, 4194304;\n"
                 "@p trap;\n"
                 "bra LAB_WAIT;\n"
                 "LAB_DONE:\n"
                 "}" :: "r"(bar), "r"(parity) : "memory");
}
__device__ __forceinline__ void tma2d(uint32_t dst, const CUtensorMap* m, int c0, int c1, uint32_t bar, u64 pol) {
    asm volatile("cp.async.bulk.tensor.2d.shared::cluster.global.mbarrier::complete_tx::bytes.L2::cache_hint "
                 "[%0], [%1, {%3, %4}], [%2], %5;"
                 :: "r"(dst), "l"(m), "r"(bar), "r"(c0), "r"(c1), "l"(pol) : "memory");
}
__device__ __forceinline__ void ldsm4(uint32_t& r0, uint32_t& r1, uint32_t& r2, uint32_t& r3, uint32_t addr) {
    asm volatile("ldmatrix.sync.aligned.m8n8.x4.shared.b16 {%0,%1,%2,%3}, [%4];"
                 : "=r"(r0), "=r"(r1), "=r"(r2), "=r"(r3) : "r"(addr) : "memory");
}
__device__ __forceinline__ void ldsm4t(uint32_t& r0, uint32_t& r1, uint32_t& r2, uint32_t& r3, uint32_t addr) {
    asm volatile("ldmatrix.sync.aligned.m8n8.x4.trans.shared.b16 {%0,%1,%2,%3}, [%4];"
                 : "=r"(r0), "=r"(r1), "=r"(r2), "=r"(r3) : "r"(addr) : "memory");
}
__device__ __forceinline__ void mma16816(float* d, uint32_t a0, uint32_t a1, uint32_t a2, uint32_t a3,
                                         uint32_t b0, uint32_t b1) {
    asm volatile("mma.sync.aligned.m16n8k16.row.col.f32.bf16.bf16.f32 {%0,%1,%2,%3}, {%4,%5,%6,%7}, {%8,%9}, {%0,%1,%2,%3};"
                 : "+f"(d[0]), "+f"(d[1]), "+f"(d[2]), "+f"(d[3])
                 : "r"(a0), "r"(a1), "r"(a2), "r"(a3), "r"(b0), "r"(b1));
}
__device__ __forceinline__ uint32_t pack_bf16(float lo, float hi) {
    uint32_t r;
    asm("cvt.rn.bf16x2.f32 %0, %1, %2;" : "=r"(r) : "f"(hi), "f"(lo));
    return r;
}
__device__ __forceinline__ float rbf(float x) { return __uint_as_float(pack_bf16(x, 0.f) << 16); }
__device__ __forceinline__ float ex2(float x) {
    float r;
    asm("ex2.approx.ftz.f32 %0, %1;" : "=f"(r) : "f"(x));
    return r;
}
__device__ __forceinline__ void init_sync() { asm volatile("barrier.sync 2, %0;" :: "n"(NTHREADS) : "memory"); }
__device__ __forceinline__ void consumer_sync() { asm volatile("bar.sync 1, 256;" ::: "memory"); }

__device__ __forceinline__ uint32_t tagw(float v, uint32_t tag4) { return ((__float_as_uint(v) + 8u) & ~15u) | tag4; }
__device__ __forceinline__ float untag(uint32_t w) { return __uint_as_float(w & ~15u); }
__device__ __forceinline__ void st_w(uint32_t* p, uint32_t v) {
    asm volatile("st.relaxed.gpu.global.u32 [%0], %1;" :: "l"(p), "r"(v) : "memory");
}
__device__ __forceinline__ void st_w2(uint32_t* p, uint32_t a, uint32_t b) {
    asm volatile("st.relaxed.gpu.global.v2.u32 [%0], {%1,%2};" :: "l"(p), "r"(a), "r"(b) : "memory");
}
__device__ __forceinline__ uint32_t ld_w(const uint32_t* p) {
    uint32_t v;
    asm volatile("ld.relaxed.gpu.global.u32 %0, [%1];" : "=r"(v) : "l"(p) : "memory");
    return v;
}
__device__ __forceinline__ bool pend4(const uint4& v, uint32_t tag4) {
    return (((v.x ^ tag4) | (v.y ^ tag4) | (v.z ^ tag4) | (v.w ^ tag4)) & 15u) != 0;
}
__device__ __forceinline__ bool pend2(const uint2& v, uint32_t tag4) { return (((v.x ^ tag4) | (v.y ^ tag4)) & 15u) != 0; }
__device__ __forceinline__ void ld4_p(bool p, const void* ptr, uint4& v) {
    asm volatile("{\n.reg .pred q;\nsetp.ne.s32 q, %5, 0;\n@q ld.relaxed.gpu.global.v4.u32 {%0,%1,%2,%3}, [%4];\n}"
                 : "+r"(v.x), "+r"(v.y), "+r"(v.z), "+r"(v.w) : "l"(ptr), "r"((int)p) : "memory");
}
__device__ __forceinline__ void ld2_p(bool p, const void* ptr, uint2& v) {
    asm volatile("{\n.reg .pred q;\nsetp.ne.s32 q, %3, 0;\n@q ld.relaxed.gpu.global.v2.u32 {%0,%1}, [%2];\n}"
                 : "+r"(v.x), "+r"(v.y) : "l"(ptr), "r"((int)p) : "memory");
}
__device__ __forceinline__ void st_slot(u64* p, uint32_t v, uint32_t tag) {
    asm volatile("{\n.reg .b64 s;\nmov.b64 s, {%1,%2};\nst.relaxed.gpu.global.b64 [%0], s;\n}" :: "l"(p), "r"(v), "r"(tag) : "memory");
}
__device__ __forceinline__ void ld_slot2_p(bool p, const u64* ptr, uint4& s) {
    asm volatile("{\n.reg .pred q;\n.reg .b64 s, t;\nsetp.ne.s32 q, %5, 0;\n"
                 "mov.b64 s, {%0,%1};\nmov.b64 t, {%2,%3};\n"
                 "@q ld.relaxed.gpu.global.v2.b64 {s,t}, [%4];\n"
                 "mov.b64 {%0,%1}, s;\nmov.b64 {%2,%3}, t;\n}"
                 : "+r"(s.x), "+r"(s.y), "+r"(s.z), "+r"(s.w) : "l"(ptr), "r"((int)p) : "memory");
}
__device__ __forceinline__ uint32_t gen_tag(uint32_t epoch, int gen) { return (epoch * NGEN + gen) % 15u + 1u; }
__device__ __forceinline__ int late_owner(int j) { return 32 - RGEN + j / NMAIN; }
__device__ __forceinline__ int late_slot(int j) { return (late_owner(j) % RGEN) * NMAIN + j % NMAIN; }

constexpr uint32_t MAIL_END = 0xffffu;
constexpr uint32_t SPIN_MAX = 1u << 22;

__global__ void __launch_bounds__(NTHREADS, 1)
fused_decode_kernel(const __grid_constant__ Params P) {
    extern __shared__ unsigned char smem_raw[];
    const uint32_t sbase = (smem_u32(smem_raw) + 1023u) & ~1023u;
    const uint32_t bar_full = sbase + SM_BAR;
    const uint32_t bar_empty = bar_full + STAGES * 8;
    const uint32_t bar_o = bar_empty + STAGES * 8;
    const int tid = threadIdx.x;
    const int cta = blockIdx.x;
    const bool fin = cta < NFIN;
    const int cbr = cta >> 6;
    const int csl = cta & 63;
    u64 pol;
    asm volatile("createpolicy.fractional.L2::evict_first.b64 %0, 1.0;" : "=l"(pol));

    if (tid == NCW * 32) {
#pragma unroll
        for (int s = 0; s < 4; s++) mbar_init(bar_full + s * 8, 1);
        asm volatile("fence.mbarrier_init.release.cluster;" ::: "memory");
        asm volatile("fence.proxy.async.shared::cta;" ::: "memory");
        if (fin) {
#pragma unroll
            for (int s = 0; s < 4; s++) {
                mbar_expect_tx(bar_full + s * 8, STAGE_BYTES);
                tma2d(sbase + SM_RING + s * STAGE_BYTES, &P.wq[cbr], csl * 64, s * 128, bar_full + s * 8, pol);
            }
        }
    }
    unsigned char* sgen = smem_raw + (sbase - smem_u32(smem_raw));
    volatile uint32_t* sMail = reinterpret_cast<volatile uint32_t*>(sgen + SM_MAIL);
    volatile uint32_t* sProg = reinterpret_cast<volatile uint32_t*>(sgen + SM_G + 8);
    volatile uint32_t* sQrdy = reinterpret_cast<volatile uint32_t*>(sgen + SM_G + 12);
    uint32_t* sQ = reinterpret_cast<uint32_t*>(sgen + SM_Q);
    const int warp = tid >> 5;
    const int lane = tid & 31;
    const uint32_t epoch = *(volatile unsigned int*)&g_epoch;
    const uint32_t tag = (epoch >= 15u ? epoch - 15u : epoch) + 1u;
    const float CS = 1.4426950408889634f;

    if (warp == NCW) {
        if (lane == 0) {
#pragma unroll
            for (int s = 4; s < STAGES; s++) mbar_init(bar_full + s * 8, 1);
#pragma unroll
            for (int s = 0; s < STAGES; s++) mbar_init(bar_empty + s * 8, NCW);
#pragma unroll
            for (int s = 0; s < 8; s++) sMail[s] = 0;
            *sProg = 0;
            *sQrdy = 0;
            mbar_init(bar_o, 2);
            asm volatile("fence.mbarrier_init.release.cluster;" ::: "memory");
            asm volatile("fence.proxy.async.shared::cta;" ::: "memory");
        }
        __syncwarp();
        asm volatile("barrier.arrive 2, %0;" :: "n"(NTHREADS) : "memory");
        if (lane == 0) {
            if (cta == 0) g_ctr[(epoch + 1) & 1] = 0;
            unsigned int* ctr = &g_ctr[epoch & 1];
            int stage = fin ? 4 : 0;
            uint32_t ph = 1;
            int lstage = 0;
            uint32_t lph = 0;
            int credit = fin ? DEPTH - 4 : DEPTH;
            uint32_t nmail = 0;
            uint32_t u = cta;
#pragma unroll 1
            while (true) {
#pragma unroll 1
                for (; credit < 4; credit++) {
                    mbar_wait(bar_full + lstage * 8, lph);
                    if (++lstage == STAGES) { lstage = 0; lph ^= 1; }
                }
                if (nmail) u = atomicAdd(ctr, 1u) + gridDim.x;
                nmail++;
                const bool last = u >= (uint32_t)UTOTAL;
                sMail[nmail & 7] = (nmail << 16) | (last ? MAIL_END : u);
                *sProg = last ? MAIL_END : u;
                if (last) {
                    if (!fin) break;
#pragma unroll 1
                    for (; credit < WO_NEED; credit++) {
                        mbar_wait(bar_full + lstage * 8, lph);
                        if (++lstage == STAGES) { lstage = 0; lph ^= 1; }
                    }
                }
                int sidx, tile;
                if (u >= (uint32_t)UMAIN) { sidx = (u - UMAIN) / NLATE; tile = NMAIN + (u - UMAIN) % NLATE; }
                else                      { sidx = u / NMAIN; tile = u - sidx * NMAIN; }
                const int row = (sidx & 15) * (SK * 2) + tile * (TILE_KEYS * 2);
                const CUtensorMap* m = last ? &P.wo[cbr] : &P.kv[(sidx >> 4) * 2];
                credit -= 4;
#pragma unroll 1
                for (int s = 0; s < 4; s++) {
                    mbar_wait(bar_empty + stage * 8, ph);
                    mbar_expect_tx(bar_full + stage * 8, STAGE_BYTES);
                    const uint32_t dst = sbase + SM_RING + stage * STAGE_BYTES;
                    if (last) {
                        tma2d(dst, m, s * 128, csl * 64, bar_full + stage * 8, pol);
                        tma2d(dst + 8192, m, s * 128 + 64, csl * 64, bar_full + stage * 8, pol);
                    } else {
                        tma2d(dst, m + (s >> 1), 0, row + (s & 1) * 128, bar_full + stage * 8, pol);
                    }
                    if (++stage == STAGES) { stage = 0; ph ^= 1; }
                }
                if (last) break;
            }
        }
        return;
    }

    if (warp == NCW + 1) {
        init_sync();
#pragma unroll 1
        for (int i = 0; i < 32; i++) {
            const u64* pq = &g_q[i * 256 + 2 * lane];
            uint4 v[4];
#pragma unroll
            for (int k = 0; k < 4; k++) v[k] = make_uint4(0u, 0u, 0u, 0u);
#pragma unroll 1
            for (uint32_t spins = 0; ; ) {
                bool any = false;
#pragma unroll
                for (int k = 0; k < 4; k++) {
                    const bool n = v[k].y != tag || v[k].w != tag;
                    any |= n;
                    ld_slot2_p(n, pq + k * 64, v[k]);
                }
                if (!any) break;
                if (++spins > SPIN_MAX) __trap();
            }
#pragma unroll
            for (int k = 0; k < 4; k++)
                *reinterpret_cast<uint2*>(&sQ[i * Q_PITCH + k * 72 + (lane >> 4) * 36 + 2 * (lane & 15)]) = make_uint2(v[k].x, v[k].z);
            __threadfence_block();
            __syncwarp();
            if (lane == 0) *sQrdy = i + 1;
        }
        return;
    }

    if (warp > NCW + 1) {
        init_sync();
        if (!fin) return;
        const int b = warp - (NCW + 2);
        const int ts = cbr * 16 + b * 8 + ((cta >> 3) & 7);
        float M = -INFINITY, L = 0.f, a0 = 0.f, a1 = 0.f, a2 = 0.f, a3 = 0.f;
#pragma unroll 1
        for (int c = 0; c <= NMAIN / 32; c++) {
            const bool isl = c == NMAIN / 32;
            const int slot0 = isl ? late_slot(ts * NLATE) : (ts % RGEN) * NMAIN + c * 32;
            const uint32_t ctag = gen_tag(epoch, isl ? NGEN - 1 : ts / RGEN);
            const uint32_t due = isl ? UMAIN + ts * NLATE + 31 + PACE_LATE : ts * NMAIN + c * 32 + 31 + PACE;
            for (uint32_t spins = 0; *sProg < due; ) {
                __nanosleep(200);
                if (++spins > SPIN_MAX) __trap();
            }
            __syncwarp();
            const uint32_t* pO = &g_partO[(size_t)(slot0 + (lane >> 4)) * 512 + (cta & 7) * 64 + 4 * (lane & 15)];
            const uint32_t* pML = &g_partML[(size_t)(((cta >> 1) & 3) * NSLOT + slot0 + lane) * 2];
            uint4 ov[16];
            uint2 ml = make_uint2(0u, 0u);
#pragma unroll
            for (int i = 0; i < 16; i++) ov[i] = make_uint4(0u, 0u, 0u, 0u);
            float w[16];
            bool have_w = false;
#pragma unroll 1
            for (uint32_t spins = 0; ; ) {
                const bool pml = pend2(ml, ctag);
                bool any = pml;
                ld2_p(pml, pML, ml);
#pragma unroll
                for (int i = 0; i < 16; i++) {
                    const bool n = pend4(ov[i], ctag);
                    any |= n;
                    ld4_p(n, pO + (size_t)i * 1024, ov[i]);
                }
                if (!have_w && !__any_sync(0xffffffffu, pml)) {
                    have_w = true;
                    const float mj = untag(ml.x);
                    float Mn = fmaxf(M, mj);
#pragma unroll
                    for (int o = 16; o > 0; o >>= 1) Mn = fmaxf(Mn, __shfl_xor_sync(0xffffffffu, Mn, o));
                    const float sc = ex2((M - Mn) * CS);
                    const float wj = ex2((mj - Mn) * CS);
                    M = Mn;
                    L = fmaf(L, sc, wj * untag(ml.y));
                    a0 *= sc; a1 *= sc; a2 *= sc; a3 *= sc;
#pragma unroll
                    for (int i = 0; i < 16; i++) w[i] = __shfl_sync(0xffffffffu, wj, 2 * i + (lane >> 4));
                    if (isl) {
#pragma unroll
                        for (int o = 16; o > 0; o >>= 1) L += __shfl_xor_sync(0xffffffffu, L, o);
                        L = 1.f / L;
                    }
                }
                if (!__any_sync(0xffffffffu, any)) break;
                if (++spins > SPIN_MAX) __trap();
            }
            if (c == NMAIN / 32 - 1 && lane == 0) st_w(&g_cons[ts * 8 + (cta & 7)], tag);
#pragma unroll
            for (int i = 0; i < 16; i++) {
                a0 = fmaf(w[i], untag(ov[i].x), a0);
                a1 = fmaf(w[i], untag(ov[i].y), a1);
                a2 = fmaf(w[i], untag(ov[i].z), a2);
                a3 = fmaf(w[i], untag(ov[i].w), a3);
            }
        }
        a0 += __shfl_xor_sync(0xffffffffu, a0, 16);
        a1 += __shfl_xor_sync(0xffffffffu, a1, 16);
        a2 += __shfl_xor_sync(0xffffffffu, a2, 16);
        a3 += __shfl_xor_sync(0xffffffffu, a3, 16);
        uint32_t* sC = reinterpret_cast<uint32_t*>(sgen + SM_C);
        if (lane < 16)
            *reinterpret_cast<uint2*>(&sC[b * 32 + 2 * lane]) = make_uint2(pack_bf16(a0 * L, a1 * L), pack_bf16(a2 * L, a3 * L));
        __syncwarp();
        if (lane == 0) mbar_arrive(bar_o);
        return;
    }

    const int g = lane >> 2;
    const int t = lane & 3;
    const int cg = warp >> 2;
    const int wq4 = warp & 3;
    float* sM = reinterpret_cast<float*>(sgen + SM_M);
    float* sL = reinterpret_cast<float*>(sgen + SM_L);
    float* sG = reinterpret_cast<float*>(sgen + SM_G);
    const float SCALE = 0.08838834764831845f;

    const int lrow = (lane & 7) + ((lane >> 4) << 3);
    const int lchk = (lane >> 3) & 1;
    int stage = 0;
    uint32_t ph = 0;

    if (fin) {
        float* sRed = reinterpret_cast<float*>(sgen + SM_RED);
        uint32_t xb[4][2];
        const uint32_t* x32 = reinterpret_cast<const uint32_t*>(P.x) + (g & 1) * 256 + cg * 64 + wq4 * 16 + t;
#pragma unroll
        for (int ks = 0; ks < 4; ks++) {
            xb[ks][0] = __ldg(x32 + (ks >> 1) * 128 + (ks & 1) * 8);
            xb[ks][1] = __ldg(x32 + (ks >> 1) * 128 + (ks & 1) * 8 + 4);
        }
        init_sync();
        float acc[4][4];
#pragma unroll
        for (int i = 0; i < 4; i++) { acc[i][0] = acc[i][1] = acc[i][2] = acc[i][3] = 0.f; }
#pragma unroll
        for (int s2 = 0; s2 < 2; s2++) {
            const int st = cg + 2 * s2;
            mbar_wait(bar_full + st * 8, 0);
            const uint32_t base = sbase + SM_RING + st * STAGE_BYTES + (wq4 * 32 + lrow) * 128;
#pragma unroll
            for (int k2 = 0; k2 < 2; k2++)
#pragma unroll
                for (int i = 0; i < 4; i++) {
                    uint32_t a0, a1, a2, a3;
                    ldsm4t(a0, a1, a2, a3, base + k2 * 2048 + (((2 * i + lchk) ^ (lane & 7)) << 4));
                    mma16816(acc[i], a0, a1, a2, a3, xb[s2 * 2 + k2][0], xb[s2 * 2 + k2][1]);
                }
        }
        __syncwarp();
        if (lane < 4) mbar_arrive(bar_empty + lane * 8);
        stage = 4;
        if (t == 0) {
#pragma unroll
            for (int i = 0; i < 4; i++) {
                sRed[warp * 128 + 0 * 64 + 16 * i + g] = acc[i][0];
                sRed[warp * 128 + 1 * 64 + 16 * i + g] = acc[i][1];
                sRed[warp * 128 + 0 * 64 + 16 * i + g + 8] = acc[i][2];
                sRed[warp * 128 + 1 * 64 + 16 * i + g + 8] = acc[i][3];
            }
        }
        consumer_sync();
        if (tid < 64) {
            float s0 = 0.f, s1 = 0.f;
#pragma unroll
            for (int w = 0; w < NCW; w++) {
                float2 v = *reinterpret_cast<const float2*>(&sRed[w * 128 + 2 * tid]);
                s0 += v.x; s1 += v.y;
            }
            st_slot(&g_q[(cbr * 2 + warp) * 2048 + csl * 32 + lane], pack_bf16(s0, s1), tag);
        } else if (tid < 128) {
            const uint4* x16 = reinterpret_cast<const uint4*>(P.x + (warp - 2) * 512);
            const uint4* g16 = reinterpret_cast<const uint4*>(P.gate_w);
            float z = 0.f;
#pragma unroll
            for (int i = 0; i < 2; i++) {
                const uint4 a = __ldg(x16 + lane + i * 32), b = __ldg(g16 + lane + i * 32);
                const uint32_t av[4] = {a.x, a.y, a.z, a.w}, bv[4] = {b.x, b.y, b.z, b.w};
#pragma unroll
                for (int k = 0; k < 4; k++) {
                    const uint32_t pr = pack_bf16(__uint_as_float(av[k] << 16) * __uint_as_float(bv[k] << 16),
                                                  __uint_as_float(av[k] & 0xffff0000u) * __uint_as_float(bv[k] & 0xffff0000u));
                    z += __uint_as_float(pr << 16) + __uint_as_float(pr & 0xffff0000u);
                }
            }
#pragma unroll
            for (int o = 16; o > 0; o >>= 1) z += __shfl_xor_sync(0xffffffffu, z, o);
            if (lane == 0) sG[warp - 2] = rbf(1.f / (1.f + expf(-rbf(z))));
        }
        uint32_t* po = &g_outp[((size_t)(warp * 8 + 2 * t) * NFIN + cta) * 8 + g];
        st_w(po, 0u);
        st_w(po + 64 * NFIN * 8, 0u);
        st_w(po + NFIN * 8, 0u);
        st_w(po + 65 * NFIN * 8, 0u);
    } else {
        init_sync();
    }

    const bool active = (g >> 2) == (t >> 1);
    uint32_t offK[2];
#pragma unroll
    for (int h = 0; h < 2; h++) {
        const int half = h ^ ((lane & 7) >> 2);
        const int swz = 2 * (lane & 3) + half;
        offK[h] = (2 * (wq4 * 16 + (lane & 7)) + half) * 128 + (((lane >> 3) ^ swz) << 4);
    }
    const uint32_t offV = (2 * lrow + cg) * 128 + (((2 * wq4 + lchk) ^ (2 * (lane & 3) + cg)) << 4);
    const uint32_t pP_w = sbase + SM_P + (g & 3) * P_PITCH + (warp * 8 + t) * 4;
    const uint32_t pP_r = sbase + SM_P + (lane & 3) * P_PITCH + (lane >> 3) * 16;

    uint32_t qseen = 0;
#pragma unroll 1
    for (uint32_t nmail = 1; ; nmail++) {
        uint32_t u = sMail[nmail & 7];
        for (uint32_t spins = 0; (u >> 16) != (nmail & 0xffffu); u = sMail[nmail & 7])
            if (++spins > (1u << 26)) __trap();
        u &= 0xffffu;
        if (u == MAIL_END) break;
        int sidx, slot;
        uint32_t ptag;
        int flag;
        if (u >= (uint32_t)UMAIN) {
            sidx = (u - UMAIN) / NLATE;
            slot = late_slot(u - UMAIN);
            ptag = gen_tag(epoch, NGEN - 1);
            flag = late_owner(u - UMAIN);
        } else {
            sidx = u / NMAIN;
            slot = (sidx % RGEN) * NMAIN + (u - sidx * NMAIN);
            ptag = gen_tag(epoch, sidx / RGEN);
            flag = sidx - RGEN;
        }
        if (qseen <= (uint32_t)sidx) {
            for (uint32_t spins = 0; (qseen = *sQrdy) <= (uint32_t)sidx; )
                if (++spins > (1u << 26)) __trap();
            __threadfence_block();
        }
        __syncwarp();
        const uint32_t* pflag = &g_cons[flag * 8 + (lane & 7)];
        uint32_t cons = tag;
        if (flag >= 0) cons = ld_w(pflag);
        uint32_t qf[2][4][2];
#pragma unroll
        for (int h = 0; h < 2; h++)
#pragma unroll
            for (int j = 0; j < 4; j++) {
                const int w0 = sidx * Q_PITCH + (g & 3) * 72 + (h ^ (g >> 2)) * 36 + 8 * j + t;
                qf[h][j][0] = sQ[w0];
                qf[h][j][1] = sQ[w0 + 4];
            }
        int s1 = stage + 1, s2 = stage + 2, s3 = stage + 3;
        uint32_t p1 = ph, p2 = ph, p3 = ph;
        if (s1 >= STAGES) { s1 -= STAGES; p1 ^= 1; }
        if (s2 >= STAGES) { s2 -= STAGES; p2 ^= 1; }
        if (s3 >= STAGES) { s3 -= STAGES; p3 ^= 1; }
        const int sk = cg ? s1 : stage;
        const uint32_t kb = sbase + SM_RING + sk * STAGE_BYTES;
        mbar_wait(bar_full + sk * 8, cg ? p1 : ph);
        float sc[2][2][4];
#pragma unroll
        for (int nt = 0; nt < 2; nt++)
#pragma unroll
            for (int h = 0; h < 2; h++) {
                sc[nt][h][0] = sc[nt][h][1] = sc[nt][h][2] = sc[nt][h][3] = 0.f;
#pragma unroll
                for (int c2 = 0; c2 < 2; c2++) {
                    uint32_t r0, r1, r2, r3;
                    ldsm4(r0, r1, r2, r3, kb + nt * 2048 + (offK[h] ^ (c2 * 64)));
                    mma16816(sc[nt][h], qf[h][2 * c2][0], 0u, qf[h][2 * c2][1], 0u, r0, r1);
                    mma16816(sc[nt][h], qf[h][2 * c2 + 1][0], 0u, qf[h][2 * c2 + 1][1], 0u, r2, r3);
                }
            }
        __syncwarp();
        if (lane < 2) mbar_arrive(bar_empty + (lane ? s1 : stage) * 8);

        const uint32_t ra = pack_bf16(sc[0][0][0] + sc[0][1][0], sc[0][0][1] + sc[0][1][1]);
        const uint32_t rb = pack_bf16(sc[1][0][0] + sc[1][1][0], sc[1][0][1] + sc[1][1][1]);
        const uint32_t sa = pack_bf16(__uint_as_float(ra << 16) * SCALE, __uint_as_float(ra & 0xffff0000u) * SCALE);
        const uint32_t sb = pack_bf16(__uint_as_float(rb << 16) * SCALE, __uint_as_float(rb & 0xffff0000u) * SCALE);
        const float v0 = __uint_as_float(sa << 16), v1 = __uint_as_float(sa & 0xffff0000u);
        const float v2 = __uint_as_float(sb << 16), v3 = __uint_as_float(sb & 0xffff0000u);
        float mx = fmaxf(fmaxf(v0, v1), fmaxf(v2, v3));
        mx = fmaxf(mx, __shfl_xor_sync(0xffffffffu, mx, 1));
        mx = fmaxf(mx, __shfl_xor_sync(0xffffffffu, mx, 18));
        if (t == 0 && g < 4) sM[g * 8 + warp] = mx;
        consumer_sync();
        const float4 ma = *reinterpret_cast<const float4*>(&sM[(g & 3) * 8]);
        const float4 mb = *reinterpret_cast<const float4*>(&sM[(g & 3) * 8 + 4]);
        const float mt = fmaxf(fmaxf(fmaxf(ma.x, ma.y), fmaxf(ma.z, ma.w)), fmaxf(fmaxf(mb.x, mb.y), fmaxf(mb.z, mb.w)));
        const float mc = mt * CS;
        const float e0 = ex2(fmaf(v0, CS, -mc));
        const float e1 = ex2(fmaf(v1, CS, -mc));
        const float e2 = ex2(fmaf(v2, CS, -mc));
        const float e3 = ex2(fmaf(v3, CS, -mc));
        if (active) {
            asm volatile("st.shared.u32 [%0], %1;" :: "r"(pP_w), "r"(pack_bf16(e0, e1)) : "memory");
            asm volatile("st.shared.u32 [%0], %1;" :: "r"(pP_w + 16), "r"(pack_bf16(e2, e3)) : "memory");
        }
        float lw = (e0 + e1) + (e2 + e3);
        lw += __shfl_xor_sync(0xffffffffu, lw, 1);
        lw += __shfl_xor_sync(0xffffffffu, lw, 18);
        if (t == 0 && g < 4) sL[g * 8 + warp] = lw;
        for (uint32_t spins = 0; cons != tag; cons = ld_w(pflag))
            if (++spins > SPIN_MAX) __trap();
        __syncwarp();
        consumer_sync();
        uint32_t pb[8][2];
#pragma unroll
        for (int q = 0; q < 4; q++)
            ldsm4(pb[2 * q][0], pb[2 * q][1], pb[2 * q + 1][0], pb[2 * q + 1][1], pP_r + q * 64);
        if (tid < 16 && t == 0) {
            const float4 la = *reinterpret_cast<const float4*>(&sL[g * 8]);
            const float4 lb = *reinterpret_cast<const float4*>(&sL[g * 8 + 4]);
            const float ls = ((la.x + la.y) + (la.z + la.w)) + ((lb.x + lb.y) + (lb.z + lb.w));
            st_w2(&g_partML[(size_t)(g * NSLOT + slot) * 2], tagw(mt, ptag), tagw(ls, ptag));
        }
        float o[2][4];
#pragma unroll
        for (int i = 0; i < 2; i++) { o[i][0] = o[i][1] = o[i][2] = o[i][3] = 0.f; }
        mbar_wait(bar_full + s2 * 8, p2);
#pragma unroll
        for (int kg = 0; kg < 4; kg++) {
            uint32_t r0, r1, r2, r3;
            ldsm4t(r0, r1, r2, r3, sbase + SM_RING + s2 * STAGE_BYTES + kg * 4096 + offV);
            mma16816(o[kg & 1], r0, r1, r2, r3, pb[kg][0], pb[kg][1]);
        }
        mbar_wait(bar_full + s3 * 8, p3);
#pragma unroll
        for (int kg = 0; kg < 4; kg++) {
            uint32_t r0, r1, r2, r3;
            ldsm4t(r0, r1, r2, r3, sbase + SM_RING + s3 * STAGE_BYTES + kg * 4096 + offV);
            mma16816(o[kg & 1], r0, r1, r2, r3, pb[4 + kg][0], pb[4 + kg][1]);
        }
        __syncwarp();
        if (lane < 2) mbar_arrive(bar_empty + (lane ? s3 : s2) * 8);
        stage += 4;
        if (stage >= STAGES) { stage -= STAGES; ph ^= 1; }
        const float y0 = (t & 2) ? o[0][2] + o[1][2] : o[0][0] + o[1][0];
        const float y1 = (t & 2) ? o[0][3] + o[1][3] : o[0][1] + o[1][1];
        uint32_t* dst = &g_partO[(size_t)slot * 512 + (t & 1) * 256 + warp * 16 + (t >> 1) * 8 + g];
        st_w(dst, tagw(y0, ptag));
        st_w(dst + 128, tagw(y1, ptag));
    }
    if (!fin) {
        if (tid == 0) st_w(&g_done[cta - NFIN], tag);
        return;
    }

    {
        const uint32_t* sC = reinterpret_cast<const uint32_t*>(sgen + SM_C);
        int st = stage + (warp >> 1);
        uint32_t sph = ph;
        if (st >= STAGES) { st -= STAGES; sph ^= 1; }
        const uint32_t base = sbase + SM_RING + st * STAGE_BYTES + (warp & 1) * 8192 + lrow * 128;
        mbar_wait(bar_full + st * 8, sph);
        uint32_t wf[4][4][4];
#pragma unroll
        for (int ks = 0; ks < 4; ks++)
#pragma unroll
            for (int i = 0; i < 4; i++)
                ldsm4t(wf[ks][i][0], wf[ks][i][1], wf[ks][i][2], wf[ks][i][3],
                       base + ks * 2048 + (((2 * i + lchk) ^ (lane & 7)) << 4));
        mbar_wait(bar_o, 0);
        float acc[4][4];
#pragma unroll
        for (int i = 0; i < 4; i++) { acc[i][0] = acc[i][1] = acc[i][2] = acc[i][3] = 0.f; }
#pragma unroll
        for (int ks = 0; ks < 4; ks++) {
            const uint32_t b0 = sC[(g & 1) * 32 + ks * 8 + t];
            const uint32_t b1 = sC[(g & 1) * 32 + ks * 8 + 4 + t];
#pragma unroll
            for (int i = 0; i < 4; i++) mma16816(acc[i], wf[ks][i][0], wf[ks][i][1], wf[ks][i][2], wf[ks][i][3], b0, b1);
        }
        float v[4];
#pragma unroll
        for (int k = 0; k < 4; k++) {
            const float lo = (t & 1) ? acc[1][k] : acc[0][k];
            const float hi = (t & 1) ? acc[3][k] : acc[2][k];
            v[k] = (t & 2) ? hi : lo;
        }
        uint32_t* po = &g_outp[((size_t)(warp * 8 + 2 * t) * NFIN + cta) * 8 + g];
        st_w(po, tagw(v[0], tag));
        st_w(po + 64 * NFIN * 8, tagw(v[1], tag));
        st_w(po + NFIN * 8, tagw(v[2], tag));
        st_w(po + 65 * NFIN * 8, tagw(v[3], tag));
    }
    {
        if (cta == 0 && warp == 1 && lane < (int)gridDim.x - NFIN) {
            for (uint32_t spins = 0; ld_w(&g_done[lane]) != tag; )
                if (++spins > SPIN_MAX) __trap();
        }
        const uint32_t* p = &g_outp[(size_t)cta * NFIN * 8 + 4 * tid];
        uint4 r = make_uint4(0u, 0u, 0u, 0u);
        for (uint32_t spins = 0; pend4(r, tag); ) {
            ld4_p(true, p, r);
            if (++spins > SPIN_MAX) __trap();
        }
        __syncwarp();
        float x0 = untag(r.x), x1 = untag(r.y), x2 = untag(r.z), x3 = untag(r.w);
#pragma unroll
        for (int o = 2; o < 32; o <<= 1) {
            x0 += __shfl_xor_sync(0xffffffffu, x0, o);
            x1 += __shfl_xor_sync(0xffffffffu, x1, o);
            x2 += __shfl_xor_sync(0xffffffffu, x2, o);
            x3 += __shfl_xor_sync(0xffffffffu, x3, o);
        }
        float* sR = reinterpret_cast<float*>(sgen + SM_R);
        if (lane < 2) *reinterpret_cast<float4*>(&sR[warp * 8 + 4 * lane]) = make_float4(x0, x1, x2, x3);
        consumer_sync();
        if (cta == 0 && tid == 32) *(volatile unsigned int*)&g_epoch = (epoch >= 29u) ? 0u : epoch + 1u;
        if (tid < 4) {
            float2 a = make_float2(0.f, 0.f), b = make_float2(0.f, 0.f);
#pragma unroll
            for (int w = 0; w < 4; w++) {
                const float2 u = *reinterpret_cast<const float2*>(&sR[w * 8 + 2 * tid]);
                const float2 v = *reinterpret_cast<const float2*>(&sR[(w + 4) * 8 + 2 * tid]);
                a.x += u.x; a.y += u.y; b.x += v.x; b.y += v.y;
            }
            const float gt = sG[cbr];
            const float gn = rbf(1.f - gt);
            const float y0 = rbf(gt * rbf(a.x)) + rbf(gn * rbf(b.x));
            const float y1 = rbf(gt * rbf(a.y)) + rbf(gn * rbf(b.y));
            reinterpret_cast<uint32_t*>(P.out)[cta * 4 + tid] = pack_bf16(y0, y1);
        }
    }
}

typedef CUresult (*EncodeFn)(CUtensorMap*, CUtensorMapDataType, cuuint32_t, void*, const cuuint64_t*,
                             const cuuint64_t*, const cuuint32_t*, const cuuint32_t*, CUtensorMapInterleave,
                             CUtensorMapSwizzle, CUtensorMapL2promotion, CUtensorMapFloatOOBfill);

void encode2d(EncodeFn enc, CUtensorMap* m, const void* ptr, uint64_t cols, uint64_t rows, uint32_t box_cols,
              uint32_t box_rows) {
    cuuint64_t dims[2] = {cols, rows};
    cuuint64_t strides[1] = {cols * 2};
    cuuint32_t box[2] = {box_cols, box_rows};
    cuuint32_t es[2] = {1, 1};
    enc(m, CU_TENSOR_MAP_DATA_TYPE_BFLOAT16, 2, const_cast<void*>(ptr), dims, strides, box, es,
        CU_TENSOR_MAP_INTERLEAVE_NONE, CU_TENSOR_MAP_SWIZZLE_128B, CU_TENSOR_MAP_L2_PROMOTION_L2_256B,
        CU_TENSOR_MAP_FLOAT_OOB_FILL_NONE);
}

}

extern "C" void kernel_launch(void* const* d_in, const int* in_sizes, int n_in, void* d_out, int out_size) {
    (void)in_sizes; (void)n_in; (void)out_size;
    static EncodeFn enc = nullptr;
    static int grid = NFIN;
    if (!enc) {
        int dev = 0, sms = 0;
        cudaGetDevice(&dev);
        cudaDeviceGetAttribute(&sms, cudaDevAttrMultiProcessorCount, dev);
        grid = sms < NFIN ? NFIN : (sms > MAX_CTA ? MAX_CTA : sms);
        cudaDriverEntryPointQueryResult qr;
        void* fn = nullptr;
        cudaGetDriverEntryPoint("cuTensorMapEncodeTiled", &fn, cudaEnableDefault, &qr);
        enc = (EncodeFn)fn;
        cudaFuncSetAttribute(fused_decode_kernel, cudaFuncAttributeMaxDynamicSharedMemorySize, SM_ALLOC);
    }
    Params P;
    const uint64_t kvrows = 2ull * 8 * SK * 2;
    encode2d(enc, &P.kv[0], d_in[1], 64, kvrows, 64, 128);
    encode2d(enc, &P.kv[1], d_in[2], 64, kvrows, 64, 128);
    encode2d(enc, &P.kv[2], d_in[6], 64, kvrows, 64, 128);
    encode2d(enc, &P.kv[3], d_in[7], 64, kvrows, 64, 128);
    encode2d(enc, &P.wq[0], d_in[3], 4096, 512, 64, 128);
    encode2d(enc, &P.wq[1], d_in[8], 4096, 512, 64, 128);
    encode2d(enc, &P.wo[0], d_in[4], 512, 4096, 64, 64);
    encode2d(enc, &P.wo[1], d_in[9], 512, 4096, 64, 64);
    P.x = (const __nv_bfloat16*)d_in[0];
    P.gate_w = (const __nv_bfloat16*)d_in[10];
    P.out = (__nv_bfloat16*)d_out;
    fused_decode_kernel<<<grid, NTHREADS, SM_ALLOC, cudaStreamPerThread>>>(P);
}
```
